```python
import torch

def _softmax(x, axis=-1):
    return torch.softmax(x, dim=axis)
def _gelu(x):
    return torch.nn.functional.gelu(x, approximate="tanh")
def _silu(x):
    return torch.nn.functional.silu(x)
def _sigmoid(x):
    return torch.sigmoid(x)
def _layernorm(x, axis=-1, eps=1e-5):
    m = x.mean(dim=axis, keepdim=True)
    v = x.var(dim=axis, keepdim=True, unbiased=False)
    return (x - m) / torch.sqrt(v + eps)
def _scatter_add(tgt, idx, src, axis=0):
    return tgt.clone().index_add_(axis, idx, src)
def _segment_sum(src, seg, n):
    out = torch.zeros((n,) + src.shape[1:], dtype=src.dtype)
    return out.index_add_(0, seg, src)
def _pad(x, pw):
    flat = tuple(v for pair in reversed(pw) for v in pair)
    return torch.nn.functional.pad(x, flat)

kernel_name = 'concat_heads__mha_block_cached__gqa_block_cached__near_ridge'

def setup_inputs():

    _w = (lambda a: (lambda t: t.to(torch.bfloat16) if t.is_floating_point() else t)(torch.as_tensor(a)))
    def _A_setup():
        B, Sq, D = 8, 144, 512
        H, Sk, Dh = 32, 1024, 128
        return {
            "x": _w((lambda *s: torch.randn(*s, dtype=torch.bfloat16) * 0.8)(B, Sq, D)),
            "k_cache": _w((lambda *s: torch.randn(*s, dtype=torch.bfloat16) * 0.8)(B, H, Sk, Dh)),
            "v_cache": _w((lambda *s: torch.randn(*s, dtype=torch.bfloat16) * 0.05)(B, H, Sk, Dh)),
            "wq": _w((lambda *s: torch.randn(*s, dtype=torch.bfloat16) * 0.8)(D, H * Dh) * (D ** -0.5)),
            "wo": _w((lambda *s: torch.randn(*s, dtype=torch.bfloat16) * 0.05)(H * Dh, D) * ((H * Dh) ** -0.5)),
        }
    _A_in = _A_setup()

    def _B_setup():
        B, Sq, D = 8, 144, 512
        Hq, Hkv, Sk, Dh = 32, 32, 1024, 128
        assert Hq % Hkv == 0, (Hq, Hkv)
        return {
            "x": _w((lambda *s: torch.randn(*s, dtype=torch.bfloat16) * 0.8)(B, Sq, D)),
            "k_cache": _w((lambda *s: torch.randn(*s, dtype=torch.bfloat16) * 0.8)(B, Hkv, Sk, Dh)),
            "v_cache": _w((lambda *s: torch.randn(*s, dtype=torch.bfloat16) * 0.05)(B, Hkv, Sk, Dh)),
            "wq": _w((lambda *s: torch.randn(*s, dtype=torch.bfloat16) * 0.8)(D, Hq * Dh) * (D ** -0.5)),
            "wo": _w((lambda *s: torch.randn(*s, dtype=torch.bfloat16) * 0.05)(Hq * Dh, D) * ((Hq * Dh) ** -0.5)),
        }
    _B_in = _B_setup()

    return {
        "A_x": _A_in["x"],
        "A_k_cache": _A_in["k_cache"],
        "A_v_cache": _A_in["v_cache"],
        "A_wq": _A_in["wq"],
        "A_wo": _A_in["wo"],
        "B_x": _B_in["x"],
        "B_k_cache": _B_in["k_cache"],
        "B_v_cache": _B_in["v_cache"],
        "B_wq": _B_in["wq"],
        "B_wo": _B_in["wo"],
    }

def reference(A_x, A_k_cache, A_v_cache, A_wq, A_wo, B_x, B_k_cache, B_v_cache, B_wq, B_wo):
    def _A_ref(x, k_cache, v_cache, wq, wo):
        B, Sq, D = x.shape
        H, Dh = 32, 128
        q = (lambda x, *d: x.permute(*d))((x @ wq).reshape(B, Sq, H, Dh), 0, 2, 1, 3)
        scores = torch.einsum("bhqd,bhkd->bhqk", q, k_cache) * (Dh ** -0.5)
        p = _softmax(scores, axis=-1)
        o = torch.einsum("bhqk,bhkd->bhqd", p, v_cache)
        return (lambda x, *d: x.permute(*d))(o, 0, 2, 1, 3).reshape(B, Sq, H * Dh) @ wo

    def _B_ref(x, k_cache, v_cache, wq, wo):
        B, Sq, D = x.shape
        Hq, Dh = 32, 128
        Hkv = k_cache.shape[1]
        rep = Hq // Hkv
        q = (lambda x, *d: x.permute(*d))((x @ wq).reshape(B, Sq, Hq, Dh), 0, 2, 1, 3)
        k = (lambda x, n, axis: torch.repeat_interleave(x, n, dim=axis))(k_cache, rep, axis=1)
        v = (lambda x, n, axis: torch.repeat_interleave(x, n, dim=axis))(v_cache, rep, axis=1)
        scores = torch.einsum("bhqd,bhkd->bhqk", q, k) * (Dh ** -0.5)
        p = _softmax(scores, axis=-1)
        o = torch.einsum("bhqk,bhkd->bhqd", p, v)
        return (lambda x, *d: x.permute(*d))(o, 0, 2, 1, 3).reshape(B, Sq, Hq * Dh) @ wo

    a = _A_ref(A_x, A_k_cache, A_v_cache, A_wq, A_wo)
    b = _B_ref(B_x, B_k_cache, B_v_cache, B_wq, B_wo)
    return torch.concatenate([a, b], axis=-1)
```

```cpp
#include <cuda_runtime.h>
#include <cuda.h>
#include <cuda_bf16.h>
#include <stdint.h>
#include <string.h>

__device__ uint32_t g_dbg[4];

namespace fk {

constexpr int SQ = 144;
constexpr int NCTA = 128;
constexpr int KV_STAGES = 4;
constexpr int KV_BYTES = 32768;
constexpr int OP_BYTES = 26624;
constexpr int HALF_IMG = 18432;
constexpr int IMG_BYTES = 36864;
constexpr int OFF_OP = KV_STAGES * KV_BYTES;
constexpr int OFF_Q = OFF_OP + 2 * OP_BYTES;
constexpr int OFF_QL = OFF_Q + 32768;
constexpr int OFF_PL = OFF_QL + 8192;
constexpr int OFF_RED = OFF_PL + 4096;
constexpr int OFF_BAR = OFF_RED + 512;
constexpr int OFF_TRS = OFF_BAR + 512;
constexpr int SMEM_BYTES = OFF_TRS + 1024 + 1024;
constexpr int BAR_FULL = 0  , BAR_EMPTY = 5  , BAR_FULL_OP = 10  , BAR_C4 = 12, BAR_QSTAGED1 = 13, BAR_EMPTY_OP = 14  , BAR_QFULL = 16  , BAR_QSTAGED = 18,
              BAR_OSTAGED = 19  , BAR_SFREE = 21, BAR_OSTAGED1 = 22, BAR_OSTORED = 23, BAR_TFULL = 24  , BAR_TEMPTY = 29  , WORD_TID = 34  , BAR_QST = 39  , WORD_SEEN = 42, WORD_TAG = 43, WORD_PROG = 44, BAR_FREE3 = 45;
constexpr int OFF_XL0 = OFF_OP + 32768;
constexpr int OFF_T3 = OFF_OP + 3 * HALF_IMG;
#define RARE(x) __builtin_expect(!!(x), 0)
#define HOTW 1
#define REGM 168
#define REGA 144
#define REGP 32
#define DISC_P 4
#define DISC 3
#define FSTG
#define OWND 2
#define DBL 0x2222
#define OPS0 18
#define MPW 4
#define MPS 100
constexpr int OP_S0 = OPS0;
constexpr uint32_t DBL3 = DBL;
#define SKP3 0x5000
constexpr uint32_t SKIP3 = SKP3;
static_assert(!(SKIP3 & DBL3), "");
constexpr int OP_LEFT = OP_S0 - 16 - __builtin_popcount(DBL3) + __builtin_popcount(SKIP3);
#define DRAIN 0
constexpr uint32_t DRN = DRAIN;
static_assert(OP_LEFT >= 0, "");
constexpr float SCALE_LOG2E = 0.08838834764831845f * 1.4426950408889634f;

struct Params {
    CUtensorMap k[2], v[2], x[2], wqa[2], wqb[2], wql[2], wo[2], out;
    const uint8_t* raw[2][4];
    uint8_t* outp;
    uint32_t zero;
    uint32_t qmask[16];
};

__device__ __align__(1024) uint8_t g_oimg[16 * 2 * 8 * IMG_BYTES];
__device__ __align__(128) uint8_t g_flag[16 * 4 * 128];
__device__ uint32_t g_epoch[NCTA];
#define DBG_HOST(code)
#define TRG()
#define TR_DECL(role, cond)
#define TR(tag)
#define TS(tag)
#define TR_END()

__device__ __forceinline__ uint32_t smem_u32(const void* p) { return (uint32_t)__cvta_generic_to_shared(p); }
__device__ __forceinline__ void mbar_init(uint32_t bar, uint32_t cnt) { asm volatile("mbarrier.init.shared::cta.b64 [%0], %1;" :: "r"(bar), "r"(cnt) : "memory"); }
__device__ __forceinline__ void mbar_expect_tx(uint32_t bar, uint32_t bytes) { asm volatile("mbarrier.arrive.expect_tx.shared::cta.b64 _, [%0], %1;" :: "r"(bar), "r"(bytes) : "memory"); }
__device__ __forceinline__ void mbar_arrive(uint32_t bar, uint32_t cnt) { asm volatile("mbarrier.arrive.shared::cta.b64 _, [%0], %1;" :: "r"(bar), "r"(cnt) : "memory"); }
__device__ __forceinline__ uint32_t mbar_try(uint32_t bar, uint32_t parity) {
    uint32_t done;
    asm volatile("{ .reg .pred p; mbarrier.try_wait.parity.shared::cta.b64 p, [%1], %2; selp.u32 %0, 1, 0, p; }" : "=r"(done) : "r"(bar), "r"(parity) : "memory");
    return done;
}
__device__ __forceinline__ uint32_t mbar_test(uint32_t bar, uint32_t parity) {
    uint32_t done;
    asm volatile("{ .reg .pred p; mbarrier.test_wait.parity.shared::cta.b64 p, [%1], %2; selp.u32 %0, 1, 0, p; }" : "=r"(done) : "r"(bar), "r"(parity) : "memory");
    return done;
}
__device__ __forceinline__ void mbar_wait(uint32_t bar, uint32_t parity, uint32_t code) {
    asm volatile("{\n.reg .pred p;\n.reg .u32 it, d;\n"
        "mbarrier.try_wait.parity.shared::cta.b64 p, [%0], %1;\n"
        "@p bra DONE;\n"
        "mov.u32 it, 0;\n"
        "LOOP:\n"
        "mbarrier.try_wait.parity.shared::cta.b64 p, [%0], %1;\n"
        "@p bra DONE;\n"
        "add.u32 it, it, 1;\n"
        "and.b32 d, it, 1023;\n"
        "setp.ne.u32 p, d, 0;\n"
        "@p bra LOOP;\n"
        "ld.volatile.global.u32 d, [g_dbg];\n"
        "setp.ne.u32 p, d, 0;\n"
        "@p bra DONE;\n"
        "setp.lt.u32 p, it, 65536;\n"
        "@p bra LOOP;\n"
        "st.volatile.global.u32 [g_dbg], it;\n"
        "DONE:\n}" :: "r"(bar), "r"(parity) : "memory");
    return;
    if (mbar_try(bar, parity)) return;
    uint32_t it = 0;
    while (!mbar_try(bar, parity)) {
        ++it;
        if ((it & 1023) == 0 && *(volatile uint32_t*)&g_dbg[0] != 0) break;
        if (it > (1u << 16)) { DBG_HOST(code); if (g_dbg[0] == 0) { g_dbg[0] = code; g_dbg[1] = blockIdx.x; g_dbg[2] = threadIdx.x; } break; }
    }
}
__device__ __forceinline__ void mbar_wait_hot(uint32_t bar, uint32_t parity, uint32_t code) {
    asm volatile("{\n.reg .pred p;\n.reg .u32 it;\n"
        "mov.u32 it, 0;\n"
        "LOOP:\n"
        "mbarrier.try_wait.parity.shared::cta.b64 p, [%0], %1;\n"
        "add.u32 it, it, 1;\n"
        "setp.lt.and.u32 p, it, 16384, !p;\n"
        "@p bra LOOP;\n}" :: "r"(bar), "r"(parity) : "memory");
}
__device__ __forceinline__ void mbar_wait_slow(uint32_t bar, uint32_t parity, uint32_t code) {
    uint32_t it = 0;
    while (!mbar_try(bar, parity)) {
        __nanosleep(256);
        if ((++it & 63) == 0) {
            uint32_t d;
            asm volatile("ld.volatile.global.u32 %0, [g_dbg];" : "=r"(d) :: "memory");
            if (d != 0 || it > (1u << 14)) {
                DBG_HOST(code);
                asm volatile("st.volatile.global.u32 [g_dbg], %0;" :: "r"(it) : "memory");
                break;
            }
        }
    }
}
__device__ __forceinline__ void tma2d(uint32_t dst, const CUtensorMap* tm, int c0, int c1, uint32_t bar) {
    asm volatile("cp.async.bulk.tensor.2d.shared::cluster.global.mbarrier::complete_tx::bytes [%0], [%1, {%3, %4}], [%2];"
        :: "r"(dst), "l"(tm), "r"(bar), "r"(c0), "r"(c1) : "memory");
}
__device__ __forceinline__ void tma2d_hint(uint32_t dst, const CUtensorMap* tm, int c0, int c1, uint32_t bar, uint64_t pol) {
    asm volatile("cp.async.bulk.tensor.2d.shared::cluster.global.mbarrier::complete_tx::bytes.L2::cache_hint [%0], [%1, {%3, %4}], [%2], %5;"
        :: "r"(dst), "l"(tm), "r"(bar), "r"(c0), "r"(c1), "l"(pol) : "memory");
}
__device__ __forceinline__ void tma3d(uint32_t dst, const CUtensorMap* tm, int c0, int c1, int c2, uint32_t bar) {
    asm volatile("cp.async.bulk.tensor.3d.shared::cluster.global.mbarrier::complete_tx::bytes [%0], [%1, {%3, %4, %5}], [%2];"
        :: "r"(dst), "l"(tm), "r"(bar), "r"(c0), "r"(c1), "r"(c2) : "memory");
}
__device__ __forceinline__ void tma4d(uint32_t dst, const CUtensorMap* tm, int c0, int c1, int c2, int c3, uint32_t bar) {
    asm volatile("cp.async.bulk.tensor.4d.shared::cluster.global.mbarrier::complete_tx::bytes [%0], [%1, {%3, %4, %5, %6}], [%2];"
        :: "r"(dst), "l"(tm), "r"(bar), "r"(c0), "r"(c1), "r"(c2), "r"(c3) : "memory");
}
__device__ __forceinline__ void tma3d_hint(uint32_t dst, const CUtensorMap* tm, int c0, int c1, int c2, uint32_t bar, uint64_t pol) {
    asm volatile("cp.async.bulk.tensor.3d.shared::cluster.global.mbarrier::complete_tx::bytes.L2::cache_hint [%0], [%1, {%3, %4, %5}], [%2], %6;"
        :: "r"(dst), "l"(tm), "r"(bar), "r"(c0), "r"(c1), "r"(c2), "l"(pol) : "memory");
}
__device__ __forceinline__ void bulk_load(uint32_t dst, const void* src, uint32_t bytes, uint32_t bar) {
    asm volatile("cp.async.bulk.shared::cluster.global.mbarrier::complete_tx::bytes [%0], [%1], %2, [%3];"
        :: "r"(dst), "l"(src), "r"(bytes), "r"(bar) : "memory");
}
__device__ __forceinline__ void prefetch_l2(const void* src, uint32_t bytes) {
    asm volatile("cp.async.bulk.prefetch.L2.global [%0], %1;" :: "l"(src), "r"(bytes) : "memory");
}
__device__ __forceinline__ void bulk_store(void* dst, uint32_t src, uint32_t bytes) {
    asm volatile("cp.async.bulk.global.shared::cta.bulk_group [%0], [%1], %2;" :: "l"(dst), "r"(src), "r"(bytes) : "memory");
}
__device__ __forceinline__ void tma2d_store(const CUtensorMap* tm, uint32_t src, int c0, int c1) {
    asm volatile("cp.async.bulk.tensor.2d.global.shared::cta.bulk_group [%0, {%2, %3}], [%1];" :: "l"(tm), "r"(src), "r"(c0), "r"(c1) : "memory");
}
__device__ __forceinline__ void bulk_commit() { asm volatile("cp.async.bulk.commit_group;" ::: "memory"); }
__device__ __forceinline__ void bulk_wait_read() { asm volatile("cp.async.bulk.wait_group.read 0;" ::: "memory"); }
__device__ __forceinline__ void bulk_wait_all() { asm volatile("cp.async.bulk.wait_group 0;" ::: "memory"); }
__device__ __forceinline__ void fence_async_smem() { asm volatile("fence.proxy.async.shared::cta;" ::: "memory"); }
__device__ __forceinline__ void named_bar(int id, int n) { asm volatile("bar.sync %0, %1;" :: "r"(id), "r"(n) : "memory"); }
__device__ __forceinline__ void named_arrive(int id, int n) { asm volatile("bar.arrive %0, %1;" :: "r"(id), "r"(n) : "memory"); }
__device__ __forceinline__ bool bar_any(int id, int n, bool c) {
    uint32_t r;
    asm volatile("{\n.reg .pred p, q;\nsetp.ne.u32 p, %3, 0;\nbar.red.or.pred q, %1, %2, p;\nselp.u32 %0, 1, 0, q;\n}" : "=r"(r) : "r"(id), "r"(n), "r"((uint32_t)c) : "memory");
    return r;
}
__device__ __forceinline__ void wg_fence() { asm volatile("wgmma.fence.sync.aligned;" ::: "memory"); }
__device__ __forceinline__ void wg_commit() { asm volatile("wgmma.commit_group.sync.aligned;" ::: "memory"); }
__device__ __forceinline__ void wg_wait0() { asm volatile("wgmma.wait_group.sync.aligned 0;" ::: "memory"); }
__device__ __forceinline__ void wg_wait1() { asm volatile("wgmma.wait_group.sync.aligned 1;" ::: "memory"); }
template <int N> __device__ __forceinline__ void fence_regs(float (&d)[N]) {
#pragma unroll
    for (int i = 0; i < N; i++) asm volatile("" : "+f"(d[i]) :: "memory");
}
__device__ __forceinline__ uint64_t make_desc(uint32_t addr, uint32_t lbo, uint32_t sbo) {
    return (uint64_t)((addr & 0x3FFFF) >> 4) | ((uint64_t)(lbo >> 4) << 16) | ((uint64_t)(sbo >> 4) << 32) | (1ull << 62);
}
__device__ __forceinline__ float ex2(float x) { float y; asm("ex2.approx.ftz.f32 %0, %1;" : "=f"(y) : "f"(x)); return y; }
__device__ __forceinline__ float max_step(float mx) {
    float t; asm("fma.rp.f32 %0, %1, %2, %3;" : "=f"(t) : "f"(mx), "f"(SCALE_LOG2E), "f"(100663296.f));
    return t - 100663296.f;
}
__device__ __forceinline__ float up8(float x) {
    float t; asm("add.rp.f32 %0, %1, %2;" : "=f"(t) : "f"(x), "f"(100663296.f));
    return t - 100663296.f;
}
__device__ __forceinline__ uint32_t pack_bf16(float lo, float hi) {
    uint32_t r; asm("cvt.rn.bf16x2.f32 %0, %1, %2;" : "=r"(r) : "f"(hi), "f"(lo)); return r;
}
__device__ __forceinline__ void stsm_x4(uint32_t addr, uint32_t r0, uint32_t r1, uint32_t r2, uint32_t r3) {
    asm volatile("stmatrix.sync.aligned.m8n8.x4.shared.b16 [%0], {%1, %2, %3, %4};" :: "r"(addr), "r"(r0), "r"(r1), "r"(r2), "r"(r3) : "memory");
}
__device__ __forceinline__ void stsm_x4_t(uint32_t addr, uint32_t r0, uint32_t r1, uint32_t r2, uint32_t r3) {
    asm volatile("stmatrix.sync.aligned.m8n8.x4.trans.shared.b16 [%0], {%1, %2, %3, %4};" :: "r"(addr), "r"(r0), "r"(r1), "r"(r2), "r"(r3) : "memory");
}

__device__ __forceinline__ void wgmma_n128_ss_kk(float (&d)[64], uint64_t da, uint64_t db, int scale_d) {
    asm volatile("{\n.reg .pred p;\nsetp.ne.b32 p, %66, 0;\n"
        "wgmma.mma_async.sync.aligned.m64n128k16.f32.bf16.bf16 "
        "{%0, %1, %2, %3, %4, %5, %6, %7, %8, %9, %10, %11, %12, %13, %14, %15, %16, %17, %18, %19, %20, %21, %22, %23, %24, %25, %26, %27, %28, %29, %30, %31, %32, %33, %34, %35, %36, %37, %38, %39, %40, %41, %42, %43, %44, %45, %46, %47, %48, %49, %50, %51, %52, %53, %54, %55, %56, %57, %58, %59, %60, %61, %62, %63}, "
        "%64, %65, p, 1, 1, 0, 0;\n}\n"
        : "+f"(d[0]), "+f"(d[1]), "+f"(d[2]), "+f"(d[3]), "+f"(d[4]), "+f"(d[5]), "+f"(d[6]), "+f"(d[7]), "+f"(d[8]), "+f"(d[9]), "+f"(d[10]), "+f"(d[11]), "+f"(d[12]), "+f"(d[13]), "+f"(d[14]), "+f"(d[15]), "+f"(d[16]), "+f"(d[17]), "+f"(d[18]), "+f"(d[19]), "+f"(d[20]), "+f"(d[21]), "+f"(d[22]), "+f"(d[23]), "+f"(d[24]), "+f"(d[25]), "+f"(d[26]), "+f"(d[27]), "+f"(d[28]), "+f"(d[29]), "+f"(d[30]), "+f"(d[31]), "+f"(d[32]), "+f"(d[33]), "+f"(d[34]), "+f"(d[35]), "+f"(d[36]), "+f"(d[37]), "+f"(d[38]), "+f"(d[39]), "+f"(d[40]), "+f"(d[41]), "+f"(d[42]), "+f"(d[43]), "+f"(d[44]), "+f"(d[45]), "+f"(d[46]), "+f"(d[47]), "+f"(d[48]), "+f"(d[49]), "+f"(d[50]), "+f"(d[51]), "+f"(d[52]), "+f"(d[53]), "+f"(d[54]), "+f"(d[55]), "+f"(d[56]), "+f"(d[57]), "+f"(d[58]), "+f"(d[59]), "+f"(d[60]), "+f"(d[61]), "+f"(d[62]), "+f"(d[63])
        : "l"(da), "l"(db), "r"(scale_d));
}
__device__ __forceinline__ void wgmma_n128_rs_n(float (&d)[64], uint32_t a0, uint32_t a1, uint32_t a2, uint32_t a3, uint64_t db, int scale_d) {
    asm volatile("{\n.reg .pred p;\nsetp.ne.b32 p, %69, 0;\n"
        "wgmma.mma_async.sync.aligned.m64n128k16.f32.bf16.bf16 "
        "{%0, %1, %2, %3, %4, %5, %6, %7, %8, %9, %10, %11, %12, %13, %14, %15, %16, %17, %18, %19, %20, %21, %22, %23, %24, %25, %26, %27, %28, %29, %30, %31, %32, %33, %34, %35, %36, %37, %38, %39, %40, %41, %42, %43, %44, %45, %46, %47, %48, %49, %50, %51, %52, %53, %54, %55, %56, %57, %58, %59, %60, %61, %62, %63}, "
        "{%64, %65, %66, %67}, %68, p, 1, 1, 1;\n}\n"
        : "+f"(d[0]), "+f"(d[1]), "+f"(d[2]), "+f"(d[3]), "+f"(d[4]), "+f"(d[5]), "+f"(d[6]), "+f"(d[7]), "+f"(d[8]), "+f"(d[9]), "+f"(d[10]), "+f"(d[11]), "+f"(d[12]), "+f"(d[13]), "+f"(d[14]), "+f"(d[15]), "+f"(d[16]), "+f"(d[17]), "+f"(d[18]), "+f"(d[19]), "+f"(d[20]), "+f"(d[21]), "+f"(d[22]), "+f"(d[23]), "+f"(d[24]), "+f"(d[25]), "+f"(d[26]), "+f"(d[27]), "+f"(d[28]), "+f"(d[29]), "+f"(d[30]), "+f"(d[31]), "+f"(d[32]), "+f"(d[33]), "+f"(d[34]), "+f"(d[35]), "+f"(d[36]), "+f"(d[37]), "+f"(d[38]), "+f"(d[39]), "+f"(d[40]), "+f"(d[41]), "+f"(d[42]), "+f"(d[43]), "+f"(d[44]), "+f"(d[45]), "+f"(d[46]), "+f"(d[47]), "+f"(d[48]), "+f"(d[49]), "+f"(d[50]), "+f"(d[51]), "+f"(d[52]), "+f"(d[53]), "+f"(d[54]), "+f"(d[55]), "+f"(d[56]), "+f"(d[57]), "+f"(d[58]), "+f"(d[59]), "+f"(d[60]), "+f"(d[61]), "+f"(d[62]), "+f"(d[63])
        : "r"(a0), "r"(a1), "r"(a2), "r"(a3), "l"(db), "r"(scale_d));
}
__device__ __forceinline__ void wgmma_n144_ss_mk(float (&d)[72], uint64_t da, uint64_t db, int scale_d) {
    asm volatile("{\n.reg .pred p;\nsetp.ne.b32 p, %74, 0;\n"
        "wgmma.mma_async.sync.aligned.m64n144k16.f32.bf16.bf16 "
        "{%0, %1, %2, %3, %4, %5, %6, %7, %8, %9, %10, %11, %12, %13, %14, %15, %16, %17, %18, %19, %20, %21, %22, %23, %24, %25, %26, %27, %28, %29, %30, %31, %32, %33, %34, %35, %36, %37, %38, %39, %40, %41, %42, %43, %44, %45, %46, %47, %48, %49, %50, %51, %52, %53, %54, %55, %56, %57, %58, %59, %60, %61, %62, %63, %64, %65, %66, %67, %68, %69, %70, %71}, "
        "%72, %73, p, 1, 1, 1, 0;\n}\n"
        : "+f"(d[0]), "+f"(d[1]), "+f"(d[2]), "+f"(d[3]), "+f"(d[4]), "+f"(d[5]), "+f"(d[6]), "+f"(d[7]), "+f"(d[8]), "+f"(d[9]), "+f"(d[10]), "+f"(d[11]), "+f"(d[12]), "+f"(d[13]), "+f"(d[14]), "+f"(d[15]), "+f"(d[16]), "+f"(d[17]), "+f"(d[18]), "+f"(d[19]), "+f"(d[20]), "+f"(d[21]), "+f"(d[22]), "+f"(d[23]), "+f"(d[24]), "+f"(d[25]), "+f"(d[26]), "+f"(d[27]), "+f"(d[28]), "+f"(d[29]), "+f"(d[30]), "+f"(d[31]), "+f"(d[32]), "+f"(d[33]), "+f"(d[34]), "+f"(d[35]), "+f"(d[36]), "+f"(d[37]), "+f"(d[38]), "+f"(d[39]), "+f"(d[40]), "+f"(d[41]), "+f"(d[42]), "+f"(d[43]), "+f"(d[44]), "+f"(d[45]), "+f"(d[46]), "+f"(d[47]), "+f"(d[48]), "+f"(d[49]), "+f"(d[50]), "+f"(d[51]), "+f"(d[52]), "+f"(d[53]), "+f"(d[54]), "+f"(d[55]), "+f"(d[56]), "+f"(d[57]), "+f"(d[58]), "+f"(d[59]), "+f"(d[60]), "+f"(d[61]), "+f"(d[62]), "+f"(d[63]), "+f"(d[64]), "+f"(d[65]), "+f"(d[66]), "+f"(d[67]), "+f"(d[68]), "+f"(d[69]), "+f"(d[70]), "+f"(d[71])
        : "l"(da), "l"(db), "r"(scale_d));
}
__device__ __forceinline__ void wgmma_n16_ss_kk(float (&d)[8], uint64_t da, uint64_t db, int scale_d) {
    asm volatile("{\n.reg .pred p;\nsetp.ne.b32 p, %10, 0;\n"
        "wgmma.mma_async.sync.aligned.m64n16k16.f32.bf16.bf16 "
        "{%0, %1, %2, %3, %4, %5, %6, %7}, "
        "%8, %9, p, 1, 1, 0, 0;\n}\n"
        : "+f"(d[0]), "+f"(d[1]), "+f"(d[2]), "+f"(d[3]), "+f"(d[4]), "+f"(d[5]), "+f"(d[6]), "+f"(d[7])
        : "l"(da), "l"(db), "r"(scale_d));
}
__device__ __forceinline__ void wgmma_n16_ss_mk(float (&d)[8], uint64_t da, uint64_t db, int scale_d) {
    asm volatile("{\n.reg .pred p;\nsetp.ne.b32 p, %10, 0;\n"
        "wgmma.mma_async.sync.aligned.m64n16k16.f32.bf16.bf16 "
        "{%0, %1, %2, %3, %4, %5, %6, %7}, "
        "%8, %9, p, 1, 1, 1, 0;\n}\n"
        : "+f"(d[0]), "+f"(d[1]), "+f"(d[2]), "+f"(d[3]), "+f"(d[4]), "+f"(d[5]), "+f"(d[6]), "+f"(d[7])
        : "l"(da), "l"(db), "r"(scale_d));
}

__device__ __forceinline__ void store_acc144_T(const float (&acc)[72], uint32_t img, int warp, int lane) {
    const int chunk = 2 * warp + ((lane >> 3) & 1);
    const int qb = ((lane >> 4) << 3) + (lane & 7);
    const uint32_t a0 = img + qb * 128 + ((chunk ^ (lane & 7)) << 4);
#pragma unroll
    for (int i = 0; i < 18; i += 2) {
        stsm_x4_t(a0 + i * 1024,
                  pack_bf16(acc[4 * i + 0], acc[4 * i + 1]), pack_bf16(acc[4 * i + 2], acc[4 * i + 3]),
                  pack_bf16(acc[4 * i + 4], acc[4 * i + 5]), pack_bf16(acc[4 * i + 6], acc[4 * i + 7]));
    }
}

template <bool ANY = false>
__device__ __forceinline__ uint32_t poll_flags(const uint8_t* f, uint32_t need, uint32_t tag, uint32_t code) {
    uint32_t seen, it = 0;
    do {
        uint32_t lo, hi;
        asm volatile("ld.acquire.gpu.global.v2.u32 {%0, %1}, [%2];" : "=r"(lo), "=r"(hi) : "l"(f) : "memory");
        lo = __vcmpeq4(lo, tag) & 0x08040201u;
        hi = __vcmpeq4(hi, tag) & 0x08040201u;
        seen = ((lo * 0x01010101u) >> 24) | (((hi * 0x01010101u) >> 24) << 4);
        if ((++it & 255) == 0) {
            asm volatile("ld.volatile.global.u32 %0, [g_dbg];" : "=r"(lo) :: "memory");
            if (lo != 0 || it > (1u << 17)) {
                DBG_HOST(code);
                asm volatile("st.volatile.global.u32 [g_dbg], %0;" :: "r"(it) : "memory");
                break;
            }
        }
    } while (ANY ? (seen & need) == 0 : (seen & need) != need);
    asm volatile("fence.proxy.async.global;" ::: "memory");
    return seen;
}
__device__ __forceinline__ void set_flag(uint8_t* f, uint32_t tag) {
    asm volatile("st.release.gpu.global.u8 [%0], %1;" :: "l"(f), "r"(tag) : "memory");
}

__global__ void __launch_bounds__(512, 1) fused_kernel(const __grid_constant__ Params p) {
    extern __shared__ uint8_t smem_raw[];
    const uint32_t sb = (smem_u32(smem_raw) + 1023) & ~1023u;
    const uint32_t bars = sb + OFF_BAR;
    const int tid = threadIdx.x, warp_id = __shfl_sync(0xffffffffu, tid >> 5, 0), lane = tid & 31;
    const int cta = blockIdx.x, grp = cta >> 3, jj = cta & 7;
    const int branch = grp >> 3, b = grp & 7;
    const uint32_t qmask = p.qmask[grp];

    if (tid == 0) {
        for (int i = 0; i < KV_STAGES + 1; i++) {
            mbar_init(bars + 8 * (BAR_FULL + i), 1);
            mbar_init(bars + 8 * (BAR_EMPTY + i), 12);
        }
        for (int i = 0; i < 3; i++) mbar_init(bars + 8 * (BAR_FULL_OP + i), 1);
        mbar_init(bars + 8 * (BAR_EMPTY_OP + 0), 4);
        mbar_init(bars + 8 * (BAR_EMPTY_OP + 1), 4);
        mbar_init(bars + 8 * (BAR_QFULL + 0), 4);
        mbar_init(bars + 8 * (BAR_QFULL + 1), 4);
        mbar_init(bars + 8 * BAR_QSTAGED, 4);
        mbar_init(bars + 8 * BAR_QSTAGED1, 4);
        mbar_init(bars + 8 * BAR_OSTAGED, 4);
        mbar_init(bars + 8 * (BAR_OSTAGED + 1), 4);
        mbar_init(bars + 8 * BAR_OSTAGED1, 4);
        asm volatile("st.shared.u32 [%0], %1;" :: "r"(bars + 8 * WORD_SEEN), "r"(0) : "memory");
        for (int i = 0; i < 3; i++) mbar_init(bars + 8 * (BAR_QST + i), 1);
        mbar_init(bars + 8 * BAR_SFREE, 1);
        mbar_init(bars + 8 * BAR_FREE3, 1);
        mbar_init(bars + 8 * BAR_OSTORED, 1);
        for (int i = 0; i < 5; i++) {
            mbar_init(bars + 8 * (BAR_TFULL + i), 1);
            mbar_init(bars + 8 * (BAR_TEMPTY + i), 4);
        }
        asm volatile("fence.mbarrier_init.release.cluster;" ::: "memory");
        for (int kc = 0; kc < 5; kc++) {
            const uint32_t st = sb + (kc < 4 ? kc * KV_BYTES : OFF_Q), fb = bars + 8 * (kc < 4 ? BAR_FULL + kc : BAR_C4);
            mbar_expect_tx(fb, 32768);
            tma2d(st, &p.x[branch], kc * 64, b * SQ, fb);
            tma3d(st + HALF_IMG, &p.wqa[branch], 0, kc * 64, jj * 2, fb);
            tma3d(st + HALF_IMG + 8192, &p.wqb[branch], 0, kc * 64, jj * 2 + 1, fb);
            if (kc == 0) {
                mbar_expect_tx(bars + 8 * BAR_FULL_OP, 16384);
                tma4d(sb + OFF_XL0, &p.wql[branch], 0, 48, 0, jj * 2 + 1, bars + 8 * BAR_FULL_OP);
            }
        }
    }
    if (tid == 32) {
        asm volatile("prefetch.tensormap [%0];" :: "l"(&p.k[branch]) : "memory");
        asm volatile("prefetch.tensormap [%0];" :: "l"(&p.v[branch]) : "memory");
        asm volatile("prefetch.tensormap [%0];" :: "l"(&p.wo[branch]) : "memory");
        asm volatile("prefetch.tensormap [%0];" :: "l"(&p.out) : "memory");
    }
    __syncthreads();

    if (warp_id >= 12) {
        asm volatile("setmaxnreg.dec.sync.aligned.u32 %0;" :: "n"(REGP));
        if (tid == 12 * 32) {
            TR_DECL(3, true)
            uint64_t pol;
            asm volatile("createpolicy.fractional.L2::evict_first.b64 %0, 1.0;" : "=l"(pol));
            int slot = 0; uint32_t ph = 0;
            auto acquire = [&](int tag) { mbar_wait(bars + 8 * (BAR_EMPTY + slot), ph, 100 + slot); TR(tag); };
            auto advance = [&]() { if (++slot == KV_STAGES) { slot = 0; ph ^= 1; } };
            auto load_kv = [&](const CUtensorMap* tm, int row, int tag) {
                acquire(tag);
                TRG();
                mbar_expect_tx(bars + 8 * (BAR_FULL + slot), 32768);
                tma3d_hint(sb + slot * KV_BYTES, tm, 0, row, 0, bars + 8 * (BAR_FULL + slot), pol);
                advance();
            };
            auto load_qp = [&](int hd, int kc0) {
                for (int kc = kc0; kc < 8; kc++) {
                    acquire(2);
                    const uint32_t st = sb + slot * KV_BYTES, fb = bars + 8 * (BAR_FULL + slot);
                    mbar_expect_tx(fb, 32768);
                    tma2d(st, &p.x[branch], kc * 64, b * SQ, fb);
                    tma3d(st + HALF_IMG, &p.wqa[branch], 0, kc * 64, hd * 2, fb);
                    tma3d(st + HALF_IMG + 8192, &p.wqb[branch], 0, kc * 64, hd * 2 + 1, fb);
                    advance();
                }
            };
            const int row0 = (b * 32 + jj) * 1024, rowr = 8192;
            mbar_expect_tx(bars + 8 * (BAR_FULL + 4), 32768);
            tma3d_hint(sb + OFF_OP, &p.k[branch], 0, row0, 0, bars + 8 * (BAR_FULL + 4), pol);
            load_qp(jj, 5);
            int qh = jj;
            for (int r = 0; r < 4; r++) {
                for (int j = 0; j < 8; j++) {
                    const int row = row0 + r * rowr + j * 128;
                    if ((qmask >> (8 * r + j)) & 1) load_qp(qh += 8, 0);
                    if (r | j) load_kv(&p.k[branch], row, 0);
                    load_kv(&p.v[branch], row, 1);
                }
                acquire(6); mbar_arrive(bars + 8 * BAR_SFREE, 1);
                if (!OWND || r < 3) advance();
            }
            for (int s = 0; s < 4; s++) {
                acquire(3);
                const uint32_t fb = bars + 8 * (BAR_FULL + slot);
                mbar_expect_tx(fb, 32768);
                for (int i = 0; i < 4; i++)
                    tma2d(sb + slot * KV_BYTES + i * 8192, &p.wo[branch], 64 * jj, 3072 + 128 * ((jj + (OWND ? 0 : 1) + 2 * s + (i >> 1)) & 7) + 64 * (i & 1), fb);
                advance();
            }
            TR_END();
        } else if (tid == 13 * 32) {
            TR_DECL(4, true)
            const uint32_t epoch1 = g_epoch[cta] + 1;
            const uint32_t tag = (epoch1 & 0xff) * 0x01010101u;
            asm volatile("st.shared.u32 [%0], %1;" :: "r"(bars + 8 * WORD_TAG), "r"(tag) : "memory");
            mbar_wait(bars + 8 * BAR_QSTAGED, 0, 298);
            mbar_wait(bars + 8 * BAR_QSTAGED1, 0, 299);
            int pos = 6, q = 0;
            for (int r = 0; r < 4; r++) {
                if (r >= 2) poll_flags(&g_flag[(grp * 4 + r - 2) * 128 + 8], 0xff, tag, 320 + r);
                if (r == 3 || (r == 2 && (DISC & 2) && (qmask >> (16 + DISC_P)))) {
                    const uint8_t* dead = g_oimg + (size_t)((grp * 2 + (r & 1)) * 8 + jj) * IMG_BYTES;
                    for (int i = 0; i < IMG_BYTES; i += 128)
                        asm volatile("discard.global.L2 [%0], 128;" :: "l"(dead + i) : "memory");
                    asm volatile("fence.acq_rel.gpu;" ::: "memory");
                    asm volatile("fence.proxy.async.global;" ::: "memory");
                }
                for (int j = 0; j < 8; j++, pos += 2) {
                    if (!((qmask >> (8 * r + j)) & 1)) continue;
                    const int s6 = (pos + 6) & 3, s7 = (pos + 7) & 3;
                    uint8_t* img = g_oimg + (size_t)((grp * 2 + (q & 1)) * 8 + jj) * IMG_BYTES;
                    pos += 8;
                    mbar_wait(bars + 8 * BAR_QSTAGED, (q + 1) & 1, 300 + q);
                    TR(0);
                    bulk_store(img, sb + s6 * KV_BYTES + HALF_IMG, 8192);
                    bulk_store(img + 8192, sb + s7 * KV_BYTES + HALF_IMG, 8192);
                    bulk_commit();
                    bulk_wait_read();
                    mbar_arrive(bars + 8 * (BAR_EMPTY + s6), 8);
                    mbar_wait(bars + 8 * BAR_QSTAGED1, (q + 1) & 1, 304 + q);
                    bulk_store(img + 16384, sb + s7 * KV_BYTES, 16384);
                    bulk_commit();
                    bulk_wait_read();
                    mbar_arrive(bars + 8 * (BAR_EMPTY + s7), 12);
                    bulk_wait_all();
                    asm volatile("fence.proxy.async.global;" ::: "memory");
                    TR(1);
                    mbar_arrive(bars + 8 * (BAR_QST + q), 1);
                    q++;
                }
                if (r < 3) {
                    mbar_wait(bars + 8 * (BAR_QFULL + 0), r & 1, 330 + r);
                    mbar_wait(bars + 8 * (BAR_QFULL + 1), r & 1, 334 + r);
                }
                uint8_t* img = g_oimg + (size_t)((grp * 2 + (r & 1)) * 8 + jj) * IMG_BYTES;
                const int sslot = pos++ & 3;
                const bool own = OWND && r == 3;
                const uint32_t st = sb + (own ? OFF_T3 : sslot * KV_BYTES), ql = own ? st + 16384 : sb + (r == 3 ? OFF_PL : OFF_QL + (r & 1) * 4096);
                const uint32_t hs = own ? HALF_IMG : 16384;
                mbar_wait(bars + 8 * BAR_OSTAGED, r & 1, 310 + r);
                bulk_store(img, st, 8192);
                bulk_store(img + HALF_IMG, st + hs, 8192);
                mbar_wait(bars + 8 * (BAR_OSTAGED + 1), r & 1, 314 + r);
                bulk_store(img + 16384, ql, 2048);
                bulk_store(img + HALF_IMG + 16384, ql + (own ? HALF_IMG : 2048), 2048);
                mbar_wait(bars + 8 * BAR_OSTAGED1, r & 1, 318 + r);
                TR(12);
                bulk_store(img + 8192, st + 8192, 8192);
                bulk_store(img + HALF_IMG + 8192, st + hs + 8192, 8192);
                bulk_commit();
                bulk_wait_read();
                mbar_arrive(bars + 8 * (own ? BAR_FREE3 : BAR_EMPTY + sslot), own ? 1 : 12);
                bulk_wait_all();
                asm volatile("fence.proxy.async.global;" ::: "memory");
                mbar_arrive(bars + 8 * BAR_OSTORED, 1);
                TR(13);
                set_flag(&g_flag[(grp * 4 + r) * 128 + jj], tag);
                TR(14);
            }
            TR_END();
        } else if (tid == 14 * 32) {
            TR_DECL(5, true)
            const uint32_t epoch1 = g_epoch[cta] + 1;
            const uint32_t tag = (epoch1 & 0xff) * 0x01010101u;
            uint32_t seen = 0, ph = 1;
            int slot = 1, pub = -1, qh = jj;
            mbar_wait(bars + 8 * (BAR_EMPTY + 4), 0, 221);
            for (int e = 0; e < 2 * (48 + OP_S0); e++) {
                const int h = e >> 1, xl = !(e & 1);
                if (xl ? (h & 1) || h >= 64 || !((qmask >> (h >> 1)) & 1) : h < OP_S0) continue;
                {
                    const int u = h - OP_S0, c = (jj + ((u & 15) >> 1)) & 7;
                    if (!xl && !(u & 1)) {
                        if ((u & 15) == 0) {
                            seen = 1u << jj;
                            mbar_wait(bars + 8 * BAR_OSTORED, (u >> 4) & 1, 230);
                        }
                        if (!((seen >> c) & 1)) seen = poll_flags(&g_flag[(grp * 4 + (u >> 4)) * 128], 1u << c, tag, 200 + (u >> 4));
                    }
                    mbar_wait(bars + 8 * (BAR_EMPTY_OP + slot), ph, 210);
                    const uint32_t st = sb + OFF_OP + slot * OP_BYTES, fb = bars + 8 * (BAR_FULL_OP + slot);
                    if (xl) {
                        mbar_expect_tx(fb, 16384);
                        tma4d(st, &p.wql[branch], 0, 48, 0, (qh += 8) * 2 + 1, fb);
                        TR(0);
                    } else {
                        mbar_expect_tx(fb, HALF_IMG + 8192);
                        tma2d(st + HALF_IMG, &p.wo[branch], 64 * jj, 1024 * (u >> 4) + 128 * c + 64 * (u & 1), fb);
                        bulk_load(st, g_oimg + (size_t)((grp * 2 + ((u >> 4) & 1)) * 8 + c) * IMG_BYTES + (u & 1) * HALF_IMG, HALF_IMG, fb);
                        TR(1);
                    }
                    if (pub >= 0 && (pub & 1) == slot) {
                        asm volatile("st.relaxed.gpu.global.u8 [%0], %1;" :: "l"(&g_flag[(grp * 4 + (pub >> 1)) * 128 + 8 + jj]), "r"(tag) : "memory");
                        pub = -1;
                    }
                    if (!xl && (u & 15) == 15 && u < 32) pub = slot | (u >> 4) << 1;
                    if (++slot == 2) { slot = 0; ph ^= 1; }
                }
            }
            mbar_wait(bars + 8 * (BAR_EMPTY_OP + slot), ph, 242);
            mbar_arrive(bars + 8 * (BAR_TEMPTY + 2 * slot), 4);
            mbar_wait(bars + 8 * (BAR_EMPTY_OP + (slot ^ 1)), ph ^ slot, 243);
            mbar_arrive(bars + 8 * (BAR_TEMPTY + 1), 4);
            mbar_arrive(bars + 8 * (BAR_TEMPTY + 2 - 2 * slot), 4);
            TR_END();
        } else if (tid == 15 * 32) {
            const uint32_t epoch1 = g_epoch[cta] + 1;
            const uint32_t tag = (epoch1 & 0xff) * 0x01010101u;
            for (int r = 0; r < 4; r++) mbar_wait_slow(bars + 8 * BAR_SFREE, r & 1, 240);
            g_epoch[cta] = epoch1;
        }
        if (tid == 14 * 32 || tid == 15 * 32) {
            const int half = tid == 14 * 32;
            uint32_t todo = 0xff & ~(1 << jj), seen = 0;
            for (int i = half, k = half; i < 14; i += 2) {
                mbar_wait(bars + 8 * (BAR_TEMPTY + k), (i >= 5 && i < 10), 244);
                if (i == 3 || i == 4) mbar_wait(bars + 8 * BAR_FREE3, 0, 245);
                if (!(seen & todo)) {
                    for (int it = 0; it < (1 << 18) && !(seen & todo); it++)
                        asm volatile("ld.acquire.cta.shared.u32 %0, [%1];" : "=r"(seen) : "r"(bars + 8 * WORD_SEEN) : "memory");
                    asm volatile("fence.proxy.async.global;" ::: "memory");
                }
                const uint32_t ready = seen & todo;
                const int c = (__ffs(((ready | ready << 8) >> (jj + 1)) | 0x100) + jj) & 7;
                todo &= ~(1u << c);
                asm volatile("st.shared.u32 [%0], %1;" :: "r"(bars + 8 * (WORD_TID + k)), "r"(((c - jj + 2) & 7) * 2 + half) : "memory");
                mbar_expect_tx(bars + 8 * (BAR_TFULL + k), HALF_IMG);
                bulk_load(sb + OFF_OP + k * HALF_IMG, g_oimg + (size_t)((grp * 2 + 1) * 8 + c) * IMG_BYTES + half * HALF_IMG, HALF_IMG, bars + 8 * (BAR_TFULL + k));
                k += 2;
                if (k >= 5) k -= 5;
            }
        }
    } else if (warp_id >= 8) {
        asm volatile("setmaxnreg.inc.sync.aligned.u32 %0;" :: "n"(REGA));
        const int w = warp_id - 8;
        TR_DECL(2, tid == 256)
        float oacc[72];
#pragma unroll
        for (int i = 0; i < 72; i++) oacc[i] = 0.f;
        int slot = 4, oslot = 1;
        uint32_t fph = 8, oph = 0;
        auto next = [&]() { const int s = slot; slot = (slot + 1 + (slot >> 2) * 2) & 3; return s; };
        auto wait_full = [&](int s, int code) { mbar_wait_hot(bars + 8 * (BAR_FULL + s), (fph >> s) & 1, code + s); fph ^= 1u << s; };
        float* red = reinterpret_cast<float*>(smem_raw + (sb - smem_u32(smem_raw)) + OFF_RED);
        auto op_mma = [&](uint32_t st, uint32_t wo = 0) {
            const uint64_t da = make_desc(wo ? wo : st + HALF_IMG, 16, 1024);
            const uint64_t db = make_desc(st, 16, 1024);
            wg_fence();
#pragma unroll
            for (int ks = 0; ks < 4; ks++)
                wgmma_n144_ss_mk(oacc, da + ks * (2048 >> 4), db + ks * (32 >> 4), 1);
        };
        auto op_wait = [&]() {
            TR(6);
            mbar_wait_hot(bars + 8 * (BAR_FULL_OP + oslot), oph, 400 + oslot);
            TR(7);
            const int s = oslot;
            if (++oslot == 2) { oslot = 0; oph ^= 1; }
            return s;
        };
        auto op_release = [&](int s) { if (lane == 0) mbar_arrive(bars + 8 * (BAR_EMPTY_OP + s), 1); };
        const uint32_t off16 = (((lane >> 4) << 3) + (lane & 7)) * 128 + (((2 * w + ((lane >> 3) & 1)) ^ (lane & 7)) << 4);
        auto store16 = [&](uint32_t base, const float (&a0)[8], const float (&a1)[8], uint32_t hs = 2048) {
            stsm_x4_t(base + off16, pack_bf16(a0[0], a0[1]), pack_bf16(a0[2], a0[3]), pack_bf16(a0[4], a0[5]), pack_bf16(a0[6], a0[7]));
            stsm_x4_t(base + off16 + hs, pack_bf16(a1[0], a1[1]), pack_bf16(a1[2], a1[3]), pack_bf16(a1[4], a1[5]), pack_bf16(a1[6], a1[7]));
        };
        const uint64_t dpl = make_desc(sb + OFF_PL, 16, 1024);
        float m[4], l[4], ol0[8], ol1[8];
#pragma unroll
        for (int c = 0; c < 4; c++) { m[c] = 0.f; l[c] = 0.f; }
#pragma unroll
        for (int i = 0; i < 8; i++) { ol0[i] = 0.f; ol1[i] = 0.f; }
        for (int r = 0; r < 4; r++) {
            const uint64_t dql = make_desc(sb + OFF_QL + (r & 1) * 4096, 16, 1024);
            for (int j = 0; j < 8; j++) {
                if ((qmask >> (8 * r + j)) & 1) { if (++oslot == 2) { oslot = 0; oph ^= 1; } }
                const bool nop = 16 * r + 2 * j >= OP_S0 && !(r == 3 && ((SKIP3 >> (2 * j)) & 1)), nopb = 16 * r + 2 * j + 1 >= OP_S0 && !(r == 3 && ((SKIP3 >> (2 * j + 1)) & 1));
                float s0[8], s1[8];
                {
                    const int kslot = next();
                    TR(0); TS(0);
                    wait_full(kslot, 420);
                    named_bar(7, 256);
                    TR(1); TS(1);
                    const uint64_t dk = make_desc(sb + kslot * KV_BYTES, 16, 1024);
                    wg_fence();
#pragma unroll
                    for (int ks = 0; ks < 8; ks++) {
                        const uint32_t ko = ((ks >> 2) * 16384 + (ks & 3) * 32) >> 4;
                        const uint32_t qo = ((ks >> 2) * 2048 + (ks & 3) * 32) >> 4;
                        wgmma_n16_ss_kk(s0, dk + ko, dql + qo, ks > 0);
                        wgmma_n16_ss_kk(s1, dk + ko + (8192 >> 4), dql + qo, ks > 0);
                    }
                    wg_commit();
                    if (nop) {
                        op_wait();
                        op_mma(sb + OFF_OP + (oslot ^ 1) * OP_BYTES);
                        wg_commit();
                        named_arrive(6, 256);
                        wg_wait1();
                    } else {
                        named_arrive(6, 256);
                        wg_wait0();
                    }
                    fence_regs(s0); fence_regs(s1);
                    TR(2); TS(2);
                    if (lane == 0) mbar_arrive(bars + 8 * (BAR_EMPTY + kslot), 1);
                }
                float tl[4];
                auto exps = [&]() {
                    float e0[8], e1[8];
#pragma unroll
                    for (int i = 0; i < 8; i++) { e0[i] = ex2(s0[i]); e1[i] = ex2(s1[i]); }
#pragma unroll
                    for (int c = 0; c < 4; c++) {
                        const int i = (c & 1) + ((c >> 1) << 2);
                        tl[c] = (e0[i] + e0[i + 2]) + (e1[i] + e1[i + 2]);
                    }
                    store16(sb + OFF_PL, e0, e1);
                    fence_async_smem();
                };
                auto col_max = [&](float (&mx)[4]) {
                    mx[0] = fmaxf(fmaxf(s0[0], s0[2]), fmaxf(s1[0], s1[2]));
                    mx[1] = fmaxf(fmaxf(s0[1], s0[3]), fmaxf(s1[1], s1[3]));
                    mx[2] = fmaxf(fmaxf(s0[4], s0[6]), fmaxf(s1[4], s1[6]));
                    mx[3] = fmaxf(fmaxf(s0[5], s0[7]), fmaxf(s1[5], s1[7]));
#pragma unroll
                    for (int c = 0; c < 4; c++) {
                        mx[c] = fmaxf(mx[c], __shfl_xor_sync(0xffffffffu, mx[c], 4));
                        mx[c] = fmaxf(mx[c], __shfl_xor_sync(0xffffffffu, mx[c], 8));
                        mx[c] = fmaxf(mx[c], __shfl_xor_sync(0xffffffffu, mx[c], 16));
                    }
                    if (lane < 4) *reinterpret_cast<float4*>(red + w * 16 + lane * 4) = make_float4(mx[0], mx[1], mx[2], mx[3]);
                    named_bar(3, 128);
                    float4 t0 = *reinterpret_cast<const float4*>(red + 0 * 16 + (lane & 3) * 4);
                    float4 t1 = *reinterpret_cast<const float4*>(red + 1 * 16 + (lane & 3) * 4);
                    float4 t2 = *reinterpret_cast<const float4*>(red + 2 * 16 + (lane & 3) * 4);
                    float4 t3 = *reinterpret_cast<const float4*>(red + 3 * 16 + (lane & 3) * 4);
                    mx[0] = fmaxf(fmaxf(t0.x, t1.x), fmaxf(t2.x, t3.x));
                    mx[1] = fmaxf(fmaxf(t0.y, t1.y), fmaxf(t2.y, t3.y));
                    mx[2] = fmaxf(fmaxf(t0.z, t1.z), fmaxf(t2.z, t3.z));
                    mx[3] = fmaxf(fmaxf(t0.w, t1.w), fmaxf(t2.w, t3.w));
                };
                if (j == 0) {
                    col_max(m);
#pragma unroll
                    for (int c = 0; c < 4; c++) { m[c] = max_step(m[c]); l[c] = 0.f; }
                }
#pragma unroll
                for (int i = 0; i < 8; i++) {
                    const int c = (i & 1) + ((i >> 2) << 1);
                    s0[i] = fmaf(s0[i], SCALE_LOG2E, -m[c]);
                    s1[i] = fmaf(s1[i], SCALE_LOG2E, -m[c]);
                }
                int im = max(__float_as_int(s0[0]), __float_as_int(s1[0]));
#pragma unroll
                for (int i = 1; i < 8; i++) im = __vimax3_s32(im, __float_as_int(s0[i]), __float_as_int(s1[i]));
                exps();
                wg_wait0();
                if (nop) op_release(oslot ^ 1);
                if ((DBL3 & 0x5555) && RARE(r == 3 && ((DBL3 >> (2 * j)) & 1))) op_release(oslot);
                if (RARE(__any_sync(0xffffffffu, bar_any(8, 128, im > 0)))) {
                    float d[4], al[4];
                    col_max(d);
#pragma unroll
                    for (int c = 0; c < 4; c++) {
                        d[c] = fmaxf(up8(d[c]), 0.f);
                        al[c] = ex2(-d[c]);
                        m[c] += d[c];
                        l[c] *= al[c];
                    }
#pragma unroll
                    for (int i = 0; i < 8; i++) {
                        const int c = (i & 1) + ((i >> 2) << 1);
                        ol0[i] *= al[c]; ol1[i] *= al[c];
                        s0[i] -= d[c]; s1[i] -= d[c];
                    }
                    exps();
                    named_bar(3, 128);
                }
#pragma unroll
                for (int c = 0; c < 4; c++) l[c] += tl[c];
                {
                    const int vslot = next();
                    TR(3); TS(3);
                    wait_full(vslot, 430);
                    named_bar(7, 256);
                    TR(4); TS(4);
                    const uint64_t dv = make_desc(sb + vslot * KV_BYTES, 16, 1024);
                    const int tok = j == 7 || (((qmask | DRN) >> (8 * r + j + 1)) & 1) ? 6 : 5;
                    wg_fence();
#pragma unroll
                    for (int kb = 0; kb < 8; kb++) {
                        const uint32_t po = ((kb >> 2) * 2048 + (kb & 3) * 32) >> 4;
                        wgmma_n16_ss_mk(ol0, dv + kb * (2048 >> 4), dpl + po, kb > 0 || j > 0);
                        wgmma_n16_ss_mk(ol1, dv + kb * (2048 >> 4) + (16384 >> 4), dpl + po, kb > 0 || j > 0);
                    }
                    wg_commit();
                    if (nopb) {
                        int n = r == 3 && ((DBL3 >> (2 * j + 1)) & 1);
#pragma unroll 1
                        do {
                            op_wait();
                            op_mma(sb + OFF_OP + (oslot ^ 1) * OP_BYTES);
                        } while (RARE(n--));
                        wg_commit();
                        named_arrive(tok, 256);
                        wg_wait1();
                    } else {
                        named_arrive(tok, 256);
                        wg_wait0();
                    }
                    fence_regs(ol0); fence_regs(ol1);
                    TR(5); TS(5);
                    if (j == 7) TR(12);
                    if (lane == 0) mbar_arrive(bars + 8 * (BAR_EMPTY + vslot), 1);
                    wg_wait0();
                    fence_regs(oacc);
                    if (nopb) op_release(oslot ^ 1);
                    if ((DBL3 & 0xaaaa) && RARE(r == 3 && ((DBL3 >> (2 * j + 1)) & 1))) op_release(oslot);
                }
            }
            float li[4];
#pragma unroll
            for (int c = 0; c < 4; c++) {
                li[c] = l[c];
                li[c] += __shfl_xor_sync(0xffffffffu, li[c], 4);
                li[c] += __shfl_xor_sync(0xffffffffu, li[c], 8);
                li[c] += __shfl_xor_sync(0xffffffffu, li[c], 16);
            }
            if (lane < 4) *reinterpret_cast<float4*>(red + 64 + w * 16 + lane * 4) = make_float4(li[0], li[1], li[2], li[3]);
            named_bar(3, 128);
            {
                float4 t0 = *reinterpret_cast<const float4*>(red + 64 + 0 * 16 + (lane & 3) * 4);
                float4 t1 = *reinterpret_cast<const float4*>(red + 64 + 1 * 16 + (lane & 3) * 4);
                float4 t2 = *reinterpret_cast<const float4*>(red + 64 + 2 * 16 + (lane & 3) * 4);
                float4 t3 = *reinterpret_cast<const float4*>(red + 64 + 3 * 16 + (lane & 3) * 4);
                li[0] = 1.f / ((t0.x + t1.x) + (t2.x + t3.x));
                li[1] = 1.f / ((t0.y + t1.y) + (t2.y + t3.y));
                li[2] = 1.f / ((t0.z + t1.z) + (t2.z + t3.z));
                li[3] = 1.f / ((t0.w + t1.w) + (t2.w + t3.w));
            }
#pragma unroll
            for (int i = 0; i < 8; i++) {
                const int c = (i & 1) + ((i >> 2) << 1);
                ol0[i] *= li[c]; ol1[i] *= li[c];
            }
            next();
            if (r == 3) mbar_wait_hot(bars + 8 * (BAR_EMPTY + 3), 1, 479);
            store16(sb + (r == 3 ? OFF_T3 + 16384 : OFF_QL + (r & 1) * 4096), ol0, ol1, r == 3 ? HALF_IMG : 2048);
            fence_async_smem();
            __syncwarp();
            if (lane == 0) mbar_arrive(bars + 8 * (BAR_OSTAGED + 1), 1);
            TR(8);
        }
        {
            uint32_t rel = 0, tph = 0, have = 0;
            for (int i = 0; i < OP_LEFT; i++) {
                TR(13);
                const int s = op_wait();
                op_mma(sb + OFF_OP + s * OP_BYTES);
                wg_commit();
                wg_wait1();
                if (rel && lane == 0) mbar_arrive(rel, 1);
                rel = bars + 8 * (BAR_EMPTY_OP + s);
            }
            {
                wg_wait0();
                if (OP_LEFT && lane == 0) mbar_arrive(rel, 1);
                wait_full(1, 475); have = 2;
                mbar_wait_hot(bars + 8 * BAR_OSTAGED, 1, 477);
                mbar_wait_hot(bars + 8 * (BAR_OSTAGED + 1), 1, 477);
                mbar_wait_hot(bars + 8 * BAR_OSTAGED1, 1, 478);
                op_mma(sb + OFF_T3, sb + KV_BYTES);
                op_mma(sb + OFF_T3 + HALF_IMG, sb + KV_BYTES + 8192);
                wg_commit();
                wg_wait0();
                if (lane == 0) { mbar_arrive(bars + 8 * (BAR_TEMPTY + 3), 1); mbar_arrive(bars + 8 * (BAR_TEMPTY + 4), 1); }
                rel = 0;
            }
            for (int i = 0, k = (OWND ? 0 : 3); i < (OWND ? 14 : 16); i++) {
                mbar_wait_hot(bars + 8 * (BAR_TFULL + k), tph, 470 + k);
                TR(14);
                uint32_t id;
                asm volatile("ld.shared.u32 %0, [%1];" : "=r"(id) : "r"(bars + 8 * (WORD_TID + k)) : "memory");
                if (!((have >> (id >> 2)) & 1)) { wait_full(id >> 2, 476); have |= 1u << (id >> 2); }
                TR(13);
                op_mma(sb + OFF_OP + k * HALF_IMG, sb + id * 8192);
                wg_commit();
                wg_wait1();
                if (rel && lane == 0) mbar_arrive(rel, 1);
                rel = bars + 8 * (BAR_TEMPTY + k);
                if (++k == 5) k = 0;
                if (k == (OWND ? 0 : 3)) tph ^= 1;
            }
            wg_wait0();
            fence_regs(oacc);
        }
        store_acc144_T(oacc, sb + OFF_OP, w, lane);
        named_bar(3, 128);
        {
            uint32_t cta2;
            asm volatile("mov.u32 %0, %%ctaid.x;" : "=r"(cta2));
            const int row = (tid & 127) >> 3, ch = tid & 7;
            uint8_t* dst = p.outp + (size_t)(((cta2 >> 3) & 7) * SQ + row) * 2048 + (cta2 >> 6) * 1024 + (cta2 & 7) * 128 + ch * 16;
            const uint32_t src = sb + OFF_OP + row * 128 + ((ch ^ (row & 7)) << 4);
            uint4 v[9];
#pragma unroll
            for (int i = 0; i < 9; i++)
                asm volatile("ld.shared.v4.u32 {%0, %1, %2, %3}, [%4];" : "=r"(v[i].x), "=r"(v[i].y), "=r"(v[i].z), "=r"(v[i].w) : "r"(src + i * 2048) : "memory");
#pragma unroll
            for (int i = 0; i < 9; i++)
                asm volatile("st.global.v4.u32 [%0], {%1, %2, %3, %4};" :: "l"(dst + i * 16 * 2048), "r"(v[i].x), "r"(v[i].y), "r"(v[i].z), "r"(v[i].w) : "memory");
        }
        if (tid == 8 * 32) {
            TR(10);
            TR(11);
            TR_END();
        }
    } else {
        asm volatile("setmaxnreg.inc.sync.aligned.u32 %0;" :: "n"(REGM));
        const int wg = warp_id >> 2, w = warp_id & 3;
        TR_DECL(wg, (tid & 127) == 0)
        int slot = 0;
        uint32_t fph = 0;
        auto next = [&]() { const int s = slot; slot = (slot + 1 + (slot >> 2) * 2) & 3; return s; };
        auto wait_full = [&](int s, int code) { mbar_wait_hot(bars + 8 * (BAR_FULL + s), (fph >> s) & 1, code + s); fph ^= 1u << s; };
        const uint64_t dq = make_desc(sb + OFF_Q + wg * 8192, 16, 1024);
        float o[64];
#pragma unroll
        for (int i = 0; i < 64; i++) o[i] = 0.f;
        float m0 = 0.f, m1 = 0.f, l0 = 0.f, l1 = 0.f;
        for (int r = -1; r < 4; r++) {
            const int jend = r < 0 ? 1 : 8;
            for (int j = 0; j < jend; j++) {
                const bool qp_here = r < 0 || ((qmask >> (8 * r + j)) & 1);
                if (RARE(qp_here)) {
                    float acc[72];
#pragma unroll
                    for (int i = 0; i < 72; i++) acc[i] = 0.f;
                    uint32_t st = 0, st6 = 0;
                    const int t = 8 * r + j;
                    const uint32_t ev = r < 0 ? 0 : 1 + __popc(qmask & ((1u << t) - 1)) + max(2 * t - OP_S0, 0);
                    uint64_t dl = make_desc(sb + (r < 0 ? OFF_XL0 : OFF_OP + (ev & 1) * OP_BYTES), 16, 1024);
                    if (wg) mbar_wait_hot(bars + 8 * (BAR_FULL_OP + (ev & 1)), (ev >> 1) & 1, 508);
                    for (int kc = 0; kc < 8; kc++) {
                        const bool c4 = r < 0 && kc == 4;
                        const int s = c4 ? 0 : next();
                        TR(6);
                        if (c4) mbar_wait_hot(bars + 8 * BAR_C4, 0, 509); else wait_full(s, 510);
                        TR(7);
                        st6 = st;
                        st = sb + (c4 ? OFF_Q : s * KV_BYTES);
                        const uint64_t da = make_desc(st + HALF_IMG + wg * 8192, 16, 1024);
                        const uint64_t db = make_desc(st, 16, 1024);
                        const uint64_t d3 = wg ? dl : da + 3 * (2048 >> 4);
                        wg_fence();
#pragma unroll
                        for (int ks = 0; ks < 4; ks++)
                            wgmma_n144_ss_mk(acc, ks == 3 ? d3 : da + ks * (2048 >> 4), db + ks * (32 >> 4), 1);
                        wg_commit();
                        wg_wait0();
                        fence_regs(acc);
                        if ((kc < 6 + wg || r < 0) && !c4 && lane == 0) mbar_arrive(bars + 8 * (BAR_EMPTY + s), 2 - wg);
                        dl += 2048 >> 4;
                    }
                    if (wg && lane == 0) mbar_arrive(bars + 8 * (BAR_EMPTY_OP + (ev & 1)), 1);
                    if (wg || r < 0) named_bar(4, 256); else named_arrive(4, 256);
                    {
                        const uint32_t off = (((lane >> 4) << 3) + (lane & 7)) * 128 + (((2 * w + ((lane >> 3) & 1)) ^ (lane & 7)) << 4);
                        const uint32_t lo = (r < 0 ? sb + OFF_Q + wg * 16384 : wg ? st : st6 + HALF_IMG) + off;
                        const uint32_t hi = r < 0 || wg ? lo : st + HALF_IMG - 8192 + off;
#pragma unroll
                        for (int i = 0; i < 18; i += 2)
                            stsm_x4_t(i < 8 ? lo + i * 1024 : i < 16 ? hi + i * 1024 : sb + OFF_QL + ((r + 1) & 1) * 4096 + wg * 2048 + off,
                                      pack_bf16(acc[4 * i + 0], acc[4 * i + 1]), pack_bf16(acc[4 * i + 2], acc[4 * i + 3]),
                                      pack_bf16(acc[4 * i + 4], acc[4 * i + 5]), pack_bf16(acc[4 * i + 6], acc[4 * i + 7]));
                    }
                    fence_async_smem();
                    __syncwarp();
                    if (lane == 0) mbar_arrive(bars + 8 * (wg ? BAR_QSTAGED1 : BAR_QSTAGED), 1);
                    if (r < 0) { mbar_wait_hot(bars + 8 * (wg ? BAR_QSTAGED : BAR_QSTAGED1), 0, 500); mbar_wait_hot(bars + 8 * (wg ? BAR_QSTAGED1 : BAR_QSTAGED), 0, 501); slot = 4; }
                }
                if (r >= 0) {
                    if (j == 0) {
                        TR(8);
                        if (r > 0) mbar_wait_hot(bars + 8 * (BAR_QFULL + wg), (r - 1) & 1, 500 + r);
                        TR(9);
                    }
                    float s[64];
                    {
                        const int kslot = next();
                        TR(0); TS(0);
                        wait_full(kslot, 520);
                        if (wg | r | j) named_bar(5 + wg, 256);
                        TR(1); TS(1);
                        const uint64_t dk = make_desc(sb + kslot * KV_BYTES, 16, 1024);
                        wg_fence();
#pragma unroll
                        for (int ks = 0; ks < 8; ks++) {
                            const uint32_t ko = ((ks >> 2) * 16384 + (ks & 3) * 32) >> 4;
                            wgmma_n128_ss_kk(s, dq + ko, dk + ko, ks > 0);
                        }
                        wg_commit();
                        named_arrive(wg ? 5 : (j == 0 || qp_here || ((DRN >> (8 * r + j)) & 1)) ? 7 : 6, 256);
                        wg_wait0();
                        fence_regs(s);
                        TR(2); TS(2);
                        if (lane == 0) {
                            mbar_arrive(bars + 8 * (BAR_EMPTY + kslot), 1);
                            if (RARE(j == 7 && r < 3)) {
                                mbar_wait(bars + 8 * (BAR_QST + r), 0, 540 + r);
                                const uint32_t off = warp_id * 2048;
                                const uint8_t* src = g_oimg + (size_t)((grp * 2 + (r & 1)) * 8 + jj) * IMG_BYTES + off;
                                mbar_expect_tx(bars + 8 * (BAR_QFULL + wg), 4096);
                                bulk_load(sb + OFF_Q + off, src, 2048, bars + 8 * (BAR_QFULL + wg));
                                bulk_load(sb + OFF_Q + off + 16384, src + 16384, 2048, bars + 8 * (BAR_QFULL + wg));
                            }
                        }
                        __syncwarp();
                    }
                    auto row_max = [&](float& mx0, float& mx1) {
                        mx0 = fmaxf(s[0], s[1]); mx1 = fmaxf(s[2], s[3]);
#pragma unroll
                        for (int i = 1; i < 16; i++) {
                            mx0 = fmaxf(mx0, fmaxf(s[4 * i], s[4 * i + 1]));
                            mx1 = fmaxf(mx1, fmaxf(s[4 * i + 2], s[4 * i + 3]));
                        }
                        mx0 = fmaxf(mx0, __shfl_xor_sync(0xffffffffu, mx0, 1));
                        mx1 = fmaxf(mx1, __shfl_xor_sync(0xffffffffu, mx1, 1));
                        mx0 = fmaxf(mx0, __shfl_xor_sync(0xffffffffu, mx0, 2));
                        mx1 = fmaxf(mx1, __shfl_xor_sync(0xffffffffu, mx1, 2));
                    };
                    if (j == 0) {
                        row_max(m0, m1);
                        m0 = max_step(m0); m1 = max_step(m1);
                        l0 = 0.f; l1 = 0.f;
                    }
#pragma unroll
                    for (int i = 0; i < 64; i++) s[i] = fmaf(s[i], SCALE_LOG2E, (i & 2) ? -m1 : -m0);
                    {
                        int ia = max(__float_as_int(s[0]), __float_as_int(s[1])), ib = max(__float_as_int(s[2]), __float_as_int(s[3]));
#pragma unroll
                        for (int i = 1; i < 16; i++) {
                            ia = __vimax3_s32(ia, __float_as_int(s[4 * i]), __float_as_int(s[4 * i + 1]));
                            ib = __vimax3_s32(ib, __float_as_int(s[4 * i + 2]), __float_as_int(s[4 * i + 3]));
                        }
                        if (RARE(__any_sync(0xffffffffu, max(ia, ib) > 0))) {
                            float d0, d1;
                            row_max(d0, d1);
                            d0 = fmaxf(up8(d0), 0.f); d1 = fmaxf(up8(d1), 0.f);
                            const float a0 = ex2(-d0), a1 = ex2(-d1);
                            m0 += d0; m1 += d1;
                            l0 *= a0; l1 *= a1;
#pragma unroll
                            for (int i = 0; i < 64; i++) {
                                s[i] -= (i & 2) ? d1 : d0;
                                o[i] *= (i & 2) ? a1 : a0;
                            }
                        }
                    }
                    float t0 = 0.f, t1 = 0.f;
                    uint32_t pr[32];
#pragma unroll
                    for (int i = 0; i < 16; i++) {
                        const float p0 = ex2(s[4 * i + 0]), p1 = ex2(s[4 * i + 1]), p2 = ex2(s[4 * i + 2]), p3 = ex2(s[4 * i + 3]);
                        t0 = i ? t0 + (p0 + p1) : p0 + p1; t1 = i ? t1 + (p2 + p3) : p2 + p3;
                        pr[2 * i] = pack_bf16(p0, p1);
                        pr[2 * i + 1] = pack_bf16(p2, p3);
                    }
                    l0 += t0; l1 += t1;
                    {
                        const int vslot = next();
                        TR(3); TS(3);
                        wait_full(vslot, 530);
                        named_bar(5 + wg + ((__float_as_uint(l0) | __float_as_uint(l1)) & p.zero), 256);
                        TR(4); TS(4);
                        const uint64_t dv = make_desc(sb + vslot * KV_BYTES, 16384, 1024);
                        wg_fence();
#pragma unroll
                        for (int kb = 0; kb < 8; kb++)
                            wgmma_n128_rs_n(o, pr[4 * kb], pr[4 * kb + 1], pr[4 * kb + 2], pr[4 * kb + 3], dv + kb * (2048 >> 4), kb > 0 || j > 0);
                        wg_commit();
                        if (!(wg == 1 && r == 3 && j == 7)) named_arrive(wg && (j == 7 || (((qmask | DRN) >> (8 * r + j + 1)) & 1)) ? 5 : 7, 256);
                        if (RARE(j == 7)) {
                            l0 += __shfl_xor_sync(0xffffffffu, l0, 1); l1 += __shfl_xor_sync(0xffffffffu, l1, 1);
                            l0 += __shfl_xor_sync(0xffffffffu, l0, 2); l1 += __shfl_xor_sync(0xffffffffu, l1, 2);
                            l0 = 1.f / l0; l1 = 1.f / l1;
                            mbar_wait_hot(bars + 8 * BAR_SFREE, r & 1, 550 + r);
                            if (OWND && r == 3) mbar_wait_hot(bars + 8 * (BAR_EMPTY + 3), 1, 555);
                        }
                        wg_wait0();
                        fence_regs(o);
                        TR(5); TS(5);
                        if (j == 7) TR(12);
                        if (lane == 0) mbar_arrive(bars + 8 * (BAR_EMPTY + vslot), 1);
                    }
                }
            }
            if (r >= 0) {
                const float i0 = l0, i1 = l1;
                const int sslot = next();
                const int q = wg * 64 + w * 16 + (((lane >> 3) & 1) << 3) + (lane & 7);
                const bool own = OWND && r == 3;
                const uint32_t rowa = sb + (own ? OFF_T3 : sslot * KV_BYTES) + q * 128, hs = own ? HALF_IMG : 16384;
#pragma unroll
                for (int i = 0; i < 16; i += 2) {
                    const int ii = i + (lane >> 4);
                    const uint32_t a = rowa + (i >> 3) * hs + (((ii & 7) ^ (lane & 7)) << 4);
                    stsm_x4(a, pack_bf16(o[4 * i] * i0, o[4 * i + 1] * i0), pack_bf16(o[4 * i + 2] * i1, o[4 * i + 3] * i1),
                               pack_bf16(o[4 * i + 4] * i0, o[4 * i + 5] * i0), pack_bf16(o[4 * i + 6] * i1, o[4 * i + 7] * i1));
                }
                fence_async_smem();
                __syncwarp();
                if (lane == 0) mbar_arrive(bars + 8 * (wg ? BAR_OSTAGED1 : BAR_OSTAGED), 1);
                TR(10);
            }
        }
        if (warp_id < MPW && lane == 0) {
            uint32_t tag, seen = 0, cta2;
            asm volatile("ld.shared.u32 %0, [%1];" : "=r"(tag) : "r"(bars + 8 * WORD_TAG) : "memory");
            asm volatile("mov.u32 %0, %%ctaid.x;" : "=r"(cta2));
            const uint8_t* f = &g_flag[((cta2 >> 3) * 4 + 3) * 128];
            __nanosleep(warp_id * MPS);
            for (int it = 0; it < (1 << 14) && seen != 0xff; it++) {
                uint32_t lo, hi;
                asm volatile("ld.acquire.gpu.global.v2.u32 {%0, %1}, [%2];" : "=r"(lo), "=r"(hi) : "l"(f) : "memory");
                lo = __vcmpeq4(lo, tag) & 0x08040201u;
                hi = __vcmpeq4(hi, tag) & 0x08040201u;
                lo = ((lo * 0x01010101u) >> 24) | (((hi * 0x01010101u) >> 24) << 4);
                if (lo != seen) {
                    seen = lo;
                    asm volatile("red.release.cta.shared.or.b32 [%0], %1;" :: "r"(bars + 8 * WORD_SEEN), "r"(lo) : "memory");
                }
            }
        }
        TR_END();
    }
}

typedef CUresult (*EncodeFn)(CUtensorMap*, CUtensorMapDataType, cuuint32_t, void*, const cuuint64_t*, const cuuint64_t*, const cuuint32_t*,
                             const cuuint32_t*, CUtensorMapInterleave, CUtensorMapSwizzle, CUtensorMapL2promotion, CUtensorMapFloatOOBfill);

static void encode(EncodeFn enc, CUtensorMap* tm, const void* base, int rank, const cuuint64_t* dims, const cuuint64_t* strides, const cuuint32_t* box) {
    cuuint32_t es[5] = {1, 1, 1, 1, 1};
    enc(tm, CU_TENSOR_MAP_DATA_TYPE_BFLOAT16, rank, const_cast<void*>(base), dims, strides, box, es, CU_TENSOR_MAP_INTERLEAVE_NONE,
        CU_TENSOR_MAP_SWIZZLE_128B, CU_TENSOR_MAP_L2_PROMOTION_L2_256B, CU_TENSOR_MAP_FLOAT_OOB_FILL_NONE);
}

}

extern "C" void kernel_launch(void* const* d_in, const int* in_sizes, int n_in, void* d_out, int out_size) {
    using namespace fk;
    static EncodeFn enc = nullptr;
    if (!enc) {
        void* fn = nullptr;
        cudaDriverEntryPointQueryResult qr;
        cudaGetDriverEntryPoint("cuTensorMapEncodeTiled", &fn, cudaEnableDefault, &qr);
        enc = (EncodeFn)fn;
        cudaFuncSetAttribute(fused_kernel, cudaFuncAttributeMaxDynamicSharedMemorySize, SMEM_BYTES);
    }
    Params p;
    memset(&p, 0, sizeof(p));
    for (int br = 0; br < 2; br++) {
        const void* x = d_in[br * 5 + 0];
        const void* k = d_in[br * 5 + 1];
        const void* v = d_in[br * 5 + 2];
        const void* wq = d_in[br * 5 + 3];
        const void* wo = d_in[br * 5 + 4];
        for (int i = 0; i < 4; i++) p.raw[br][i] = (const uint8_t*)d_in[br * 5 + i];
        {
            cuuint64_t dims[3] = {64, 262144, 2}, str[2] = {256, 128};
            cuuint32_t box[3] = {64, 128, 2};
            encode(enc, &p.k[br], k, 3, dims, str, box);
            encode(enc, &p.v[br], v, 3, dims, str, box);
        }
        {
            cuuint64_t dims[2] = {512, 1152}, str[1] = {1024};
            cuuint32_t box[2] = {64, 144};
            encode(enc, &p.x[br], x, 2, dims, str, box);
        }
        {
            cuuint64_t dims[3] = {64, 512, 64}, str[2] = {8192, 128};
            cuuint32_t box[3] = {64, 64, 1};
            encode(enc, &p.wqa[br], wq, 3, dims, str, box);
            box[1] = 48;
            encode(enc, &p.wqb[br], wq, 3, dims, str, box);
        }
        {
            cuuint64_t dims[4] = {64, 64, 8, 64}, str[3] = {8192, 64 * 8192, 128};
            cuuint32_t box[4] = {64, 16, 8, 1};
            encode(enc, &p.wql[br], wq, 4, dims, str, box);
        }
        {
            cuuint64_t dims[2] = {512, 4096}, str[1] = {1024};
            cuuint32_t box[2] = {64, 64};
            encode(enc, &p.wo[br], wo, 2, dims, str, box);
        }
    }
    {
        cuuint64_t dims[2] = {1024, 1152}, str[1] = {2048};
        cuuint32_t box[2] = {64, 144};
        encode(enc, &p.out, d_out, 2, dims, str, box);
    }
    p.outp = (uint8_t*)d_out;
    const unsigned char qpos[16][3] = {{3, 12, 22}, {1, 15, 19}, {1, 15, 23}, {3, 15, 17}, {4, 12, 21}, {1, 9, 18}, {4, 9, 17}, {2, 13, 17}, {7, 10, 20}, {5, 14, 23}, {7, 9, 20}, {5, 11, 20}, {4, 12, 17}, {7, 13, 22}, {4, 14, 21}, {6, 9, 17}};
    for (int g = 0; g < 16; g++) p.qmask[g] = 1u << qpos[g][0] | 1u << qpos[g][1] | 1u << qpos[g][2];
    fused_kernel<<<NCTA, 512, SMEM_BYTES>>>(p);
}
```
